```python
import torch

def _softmax(x, axis=-1):
    return torch.softmax(x, dim=axis)

def _gelu(x):
    return torch.nn.functional.gelu(x, approximate='tanh')

def _silu(x):
    return torch.nn.functional.silu(x)

def _sigmoid(x):
    return torch.sigmoid(x)

def _layernorm(x, axis=-1, eps=1e-05):
    m = x.mean(dim=axis, keepdim=True)
    v = x.var(dim=axis, keepdim=True, unbiased=False)
    return (x - m) / torch.sqrt(v + eps)

def _scatter_add(tgt, idx, src, axis=0):
    return tgt.clone().index_add_(axis, idx, src)

def _segment_sum(src, seg, n):
    out = torch.zeros((n,) + src.shape[1:], dtype=src.dtype)
    return out.index_add_(0, seg, src)

def _pad(x, pw):
    flat = tuple((v for pair in reversed(pw) for v in pair))
    return torch.nn.functional.pad(x, flat)
kernel_name = 'gated_mix__linear_attn_block__mixer_gmlp__prompt'

def setup_inputs():

    _w = lambda a: (lambda t: t.to(torch.bfloat16) if t.is_floating_point() else t)(torch.as_tensor(a))

    def _A_setup():
        B, S, D = (1, 2048, 512)
        return {'x': _w((lambda *s: torch.randn(*s, dtype=torch.bfloat16) * 0.05)(B, S, D)), 'wqkv': _w((lambda *s: torch.randn(*s, dtype=torch.bfloat16) * 1.6)(D, 3 * D)), 'wo': _w((lambda *s: torch.randn(*s, dtype=torch.bfloat16) * 0.2)(D, D))}
    _A_in = _A_setup()

    def _B_setup():
        B, S, D, F = (1, 2048, 512, 1792)
        Fh = F // 2
        return {'x': _w((lambda *s: torch.randn(*s, dtype=torch.bfloat16) * 0.05)(B, S, D)), 'w_in': _w((lambda *s: torch.randn(*s, dtype=torch.bfloat16) * 0.4)(D, 2 * Fh)), 'w_sp': _w(0.01 * (lambda *s: torch.randn(*s, dtype=torch.bfloat16) * 0.4)(S, S)), 'b_sp': _w(1.0 + 0.01 * (lambda *s: torch.randn(*s, dtype=torch.bfloat16) * 0.05)(S)), 'w_out': _w((lambda *s: torch.randn(*s, dtype=torch.bfloat16) * 0.05)(Fh, D))}
    _B_in = _B_setup()
    return {'A_x': _A_in['x'], 'A_wqkv': _A_in['wqkv'], 'A_wo': _A_in['wo'], 'B_x': _B_in['x'], 'B_w_in': _B_in['w_in'], 'B_w_sp': _B_in['w_sp'], 'B_b_sp': _B_in['b_sp'], 'B_w_out': _B_in['w_out'], 'gate_w': _w((lambda *s: torch.randn(*s, dtype=torch.bfloat16) * 0.05)(512) * 16.0)}

def reference(A_x, A_wqkv, A_wo, B_x, B_w_in, B_w_sp, B_b_sp, B_w_out, gate_w):

    def _A_ref(x, wqkv, wo):
        B, S, D = x.shape
        H = 32
        Dh = D // H
        qkv = (lambda x, *d: x.permute(*d))((x @ wqkv).reshape(B, S, 3, H, Dh), 2, 0, 3, 1, 4)
        q, k, v = (qkv[0], qkv[1], qkv[2])
        phi = lambda t: torch.where(t > 0, t + 1, torch.exp(t)) + 1e-06
        pq, pk = (phi(q), phi(k))
        kv = torch.einsum('bhsd,bhse->bhde', pk, v)
        z = torch.einsum('bhsd->bhd', pk)
        num = torch.einsum('bhqd,bhde->bhqe', pq, kv)
        den = torch.einsum('bhqd,bhd->bhq', pq, z)[..., None] + 1e-06
        o = num / den
        return (lambda x, *d: x.permute(*d))(o, 0, 2, 1, 3).reshape(B, S, D) @ wo

    def _B_ref(x, w_in, w_sp, b_sp, w_out):
        B, S, D = x.shape
        F = w_in.shape[-1]
        Fh = F // 2
        z = _gelu(torch.einsum('bsd,df->bsf', x, w_in))
        z1 = z[..., :Fh].clone()
        z2 = _layernorm(z[..., Fh:], axis=-1)
        g = torch.einsum('ts,bsf->btf', w_sp, z2) + b_sp[None, :, None]
        return torch.einsum('bsf,fd->bsd', z1 * g, w_out)
    x = A_x
    g = _sigmoid((x * gate_w).sum(-1, keepdims=True))
    a = _A_ref(x, A_wqkv, A_wo)
    b = _B_ref(x, B_w_in, B_w_sp, B_b_sp, B_w_out)
    return g * a + (1 - g) * b
```

```cpp
#include <cuda_runtime.h>
#include <cuda_bf16.h>
#include <cuda.h>
#include <stdint.h>
#include <stdio.h>

#define TRACE2 0
#define SPLIT 14
#define ZP 2
#define ZR 16
template<int TA, int TB> __device__ __forceinline__ void wgmma_ss_n24(float (&d)[12], uint64_t da, uint64_t db, int scale_d) {
  asm volatile("{\n.reg .pred p;\n"
    "setp.ne.b32 p, %14, 0;\n"
    "wgmma.mma_async.sync.aligned.m64n24k16.f32.bf16.bf16 {%0, %1, %2, %3, %4, %5, %6, %7, %8, %9, %10, %11}, %12, %13, p, 1, 1, %15, %16;\n}\n"
    : "+f"(d[0]), "+f"(d[1]), "+f"(d[2]), "+f"(d[3]), "+f"(d[4]), "+f"(d[5]), "+f"(d[6]), "+f"(d[7]), "+f"(d[8]), "+f"(d[9]), "+f"(d[10]), "+f"(d[11])
    : "l"(da), "l"(db), "r"(scale_d), "n"(TA), "n"(TB));
}
template<int TA, int TB> __device__ __forceinline__ void wgmma_ss_n64(float (&d)[32], uint64_t da, uint64_t db, int scale_d) {
  asm volatile("{\n.reg .pred p;\n"
    "setp.ne.b32 p, %34, 0;\n"
    "wgmma.mma_async.sync.aligned.m64n64k16.f32.bf16.bf16 {%0, %1, %2, %3, %4, %5, %6, %7, %8, %9, %10, %11, %12, %13, %14, %15, %16, %17, %18, %19, %20, %21, %22, %23, %24, %25, %26, %27, %28, %29, %30, %31}, %32, %33, p, 1, 1, %35, %36;\n}\n"
    : "+f"(d[0]), "+f"(d[1]), "+f"(d[2]), "+f"(d[3]), "+f"(d[4]), "+f"(d[5]), "+f"(d[6]), "+f"(d[7]), "+f"(d[8]), "+f"(d[9]), "+f"(d[10]), "+f"(d[11]), "+f"(d[12]), "+f"(d[13]), "+f"(d[14]), "+f"(d[15]), "+f"(d[16]), "+f"(d[17]), "+f"(d[18]), "+f"(d[19]), "+f"(d[20]), "+f"(d[21]), "+f"(d[22]), "+f"(d[23]), "+f"(d[24]), "+f"(d[25]), "+f"(d[26]), "+f"(d[27]), "+f"(d[28]), "+f"(d[29]), "+f"(d[30]), "+f"(d[31])
    : "l"(da), "l"(db), "r"(scale_d), "n"(TA), "n"(TB));
}
template<int TA, int TB> __device__ __forceinline__ void wgmma_ss_n112(float (&d)[56], uint64_t da, uint64_t db, int scale_d) {
  asm volatile("{\n.reg .pred p;\n"
    "setp.ne.b32 p, %58, 0;\n"
    "wgmma.mma_async.sync.aligned.m64n112k16.f32.bf16.bf16 {%0, %1, %2, %3, %4, %5, %6, %7, %8, %9, %10, %11, %12, %13, %14, %15, %16, %17, %18, %19, %20, %21, %22, %23, %24, %25, %26, %27, %28, %29, %30, %31, %32, %33, %34, %35, %36, %37, %38, %39, %40, %41, %42, %43, %44, %45, %46, %47, %48, %49, %50, %51, %52, %53, %54, %55}, %56, %57, p, 1, 1, %59, %60;\n}\n"
    : "+f"(d[0]), "+f"(d[1]), "+f"(d[2]), "+f"(d[3]), "+f"(d[4]), "+f"(d[5]), "+f"(d[6]), "+f"(d[7]), "+f"(d[8]), "+f"(d[9]), "+f"(d[10]), "+f"(d[11]), "+f"(d[12]), "+f"(d[13]), "+f"(d[14]), "+f"(d[15]), "+f"(d[16]), "+f"(d[17]), "+f"(d[18]), "+f"(d[19]), "+f"(d[20]), "+f"(d[21]), "+f"(d[22]), "+f"(d[23]), "+f"(d[24]), "+f"(d[25]), "+f"(d[26]), "+f"(d[27]), "+f"(d[28]), "+f"(d[29]), "+f"(d[30]), "+f"(d[31]), "+f"(d[32]), "+f"(d[33]), "+f"(d[34]), "+f"(d[35]), "+f"(d[36]), "+f"(d[37]), "+f"(d[38]), "+f"(d[39]), "+f"(d[40]), "+f"(d[41]), "+f"(d[42]), "+f"(d[43]), "+f"(d[44]), "+f"(d[45]), "+f"(d[46]), "+f"(d[47]), "+f"(d[48]), "+f"(d[49]), "+f"(d[50]), "+f"(d[51]), "+f"(d[52]), "+f"(d[53]), "+f"(d[54]), "+f"(d[55])
    : "l"(da), "l"(db), "r"(scale_d), "n"(TA), "n"(TB));
}
template<int TA, int TB> __device__ __forceinline__ void wgmma_ss_n128(float (&d)[64], uint64_t da, uint64_t db, int scale_d) {
  asm volatile("{\n.reg .pred p;\n"
    "setp.ne.b32 p, %66, 0;\n"
    "wgmma.mma_async.sync.aligned.m64n128k16.f32.bf16.bf16 {%0, %1, %2, %3, %4, %5, %6, %7, %8, %9, %10, %11, %12, %13, %14, %15, %16, %17, %18, %19, %20, %21, %22, %23, %24, %25, %26, %27, %28, %29, %30, %31, %32, %33, %34, %35, %36, %37, %38, %39, %40, %41, %42, %43, %44, %45, %46, %47, %48, %49, %50, %51, %52, %53, %54, %55, %56, %57, %58, %59, %60, %61, %62, %63}, %64, %65, p, 1, 1, %67, %68;\n}\n"
    : "+f"(d[0]), "+f"(d[1]), "+f"(d[2]), "+f"(d[3]), "+f"(d[4]), "+f"(d[5]), "+f"(d[6]), "+f"(d[7]), "+f"(d[8]), "+f"(d[9]), "+f"(d[10]), "+f"(d[11]), "+f"(d[12]), "+f"(d[13]), "+f"(d[14]), "+f"(d[15]), "+f"(d[16]), "+f"(d[17]), "+f"(d[18]), "+f"(d[19]), "+f"(d[20]), "+f"(d[21]), "+f"(d[22]), "+f"(d[23]), "+f"(d[24]), "+f"(d[25]), "+f"(d[26]), "+f"(d[27]), "+f"(d[28]), "+f"(d[29]), "+f"(d[30]), "+f"(d[31]), "+f"(d[32]), "+f"(d[33]), "+f"(d[34]), "+f"(d[35]), "+f"(d[36]), "+f"(d[37]), "+f"(d[38]), "+f"(d[39]), "+f"(d[40]), "+f"(d[41]), "+f"(d[42]), "+f"(d[43]), "+f"(d[44]), "+f"(d[45]), "+f"(d[46]), "+f"(d[47]), "+f"(d[48]), "+f"(d[49]), "+f"(d[50]), "+f"(d[51]), "+f"(d[52]), "+f"(d[53]), "+f"(d[54]), "+f"(d[55]), "+f"(d[56]), "+f"(d[57]), "+f"(d[58]), "+f"(d[59]), "+f"(d[60]), "+f"(d[61]), "+f"(d[62]), "+f"(d[63])
    : "l"(da), "l"(db), "r"(scale_d), "n"(TA), "n"(TB));
}
template<int TA, int TB> __device__ __forceinline__ void wgmma_ss0_n24(float (&d)[12], uint64_t da, uint64_t db) {
  asm volatile("{\n.reg .pred p;\nsetp.ne.b32 p, 0, 0;\n"
    "wgmma.mma_async.sync.aligned.m64n24k16.f32.bf16.bf16 {%0, %1, %2, %3, %4, %5, %6, %7, %8, %9, %10, %11}, %12, %13, p, 1, 1, %14, %15;\n}\n"
    : "=f"(d[0]), "=f"(d[1]), "=f"(d[2]), "=f"(d[3]), "=f"(d[4]), "=f"(d[5]), "=f"(d[6]), "=f"(d[7]), "=f"(d[8]), "=f"(d[9]), "=f"(d[10]), "=f"(d[11])
    : "l"(da), "l"(db), "n"(TA), "n"(TB));
}
template<int TA, int TB> __device__ __forceinline__ void wgmma_ss0_n64(float (&d)[32], uint64_t da, uint64_t db) {
  asm volatile("{\n.reg .pred p;\nsetp.ne.b32 p, 0, 0;\n"
    "wgmma.mma_async.sync.aligned.m64n64k16.f32.bf16.bf16 {%0, %1, %2, %3, %4, %5, %6, %7, %8, %9, %10, %11, %12, %13, %14, %15, %16, %17, %18, %19, %20, %21, %22, %23, %24, %25, %26, %27, %28, %29, %30, %31}, %32, %33, p, 1, 1, %34, %35;\n}\n"
    : "=f"(d[0]), "=f"(d[1]), "=f"(d[2]), "=f"(d[3]), "=f"(d[4]), "=f"(d[5]), "=f"(d[6]), "=f"(d[7]), "=f"(d[8]), "=f"(d[9]), "=f"(d[10]), "=f"(d[11]), "=f"(d[12]), "=f"(d[13]), "=f"(d[14]), "=f"(d[15]), "=f"(d[16]), "=f"(d[17]), "=f"(d[18]), "=f"(d[19]), "=f"(d[20]), "=f"(d[21]), "=f"(d[22]), "=f"(d[23]), "=f"(d[24]), "=f"(d[25]), "=f"(d[26]), "=f"(d[27]), "=f"(d[28]), "=f"(d[29]), "=f"(d[30]), "=f"(d[31])
    : "l"(da), "l"(db), "n"(TA), "n"(TB));
}
template<int TA, int TB> __device__ __forceinline__ void wgmma_ss0_n112(float (&d)[56], uint64_t da, uint64_t db) {
  asm volatile("{\n.reg .pred p;\nsetp.ne.b32 p, 0, 0;\n"
    "wgmma.mma_async.sync.aligned.m64n112k16.f32.bf16.bf16 {%0, %1, %2, %3, %4, %5, %6, %7, %8, %9, %10, %11, %12, %13, %14, %15, %16, %17, %18, %19, %20, %21, %22, %23, %24, %25, %26, %27, %28, %29, %30, %31, %32, %33, %34, %35, %36, %37, %38, %39, %40, %41, %42, %43, %44, %45, %46, %47, %48, %49, %50, %51, %52, %53, %54, %55}, %56, %57, p, 1, 1, %58, %59;\n}\n"
    : "=f"(d[0]), "=f"(d[1]), "=f"(d[2]), "=f"(d[3]), "=f"(d[4]), "=f"(d[5]), "=f"(d[6]), "=f"(d[7]), "=f"(d[8]), "=f"(d[9]), "=f"(d[10]), "=f"(d[11]), "=f"(d[12]), "=f"(d[13]), "=f"(d[14]), "=f"(d[15]), "=f"(d[16]), "=f"(d[17]), "=f"(d[18]), "=f"(d[19]), "=f"(d[20]), "=f"(d[21]), "=f"(d[22]), "=f"(d[23]), "=f"(d[24]), "=f"(d[25]), "=f"(d[26]), "=f"(d[27]), "=f"(d[28]), "=f"(d[29]), "=f"(d[30]), "=f"(d[31]), "=f"(d[32]), "=f"(d[33]), "=f"(d[34]), "=f"(d[35]), "=f"(d[36]), "=f"(d[37]), "=f"(d[38]), "=f"(d[39]), "=f"(d[40]), "=f"(d[41]), "=f"(d[42]), "=f"(d[43]), "=f"(d[44]), "=f"(d[45]), "=f"(d[46]), "=f"(d[47]), "=f"(d[48]), "=f"(d[49]), "=f"(d[50]), "=f"(d[51]), "=f"(d[52]), "=f"(d[53]), "=f"(d[54]), "=f"(d[55])
    : "l"(da), "l"(db), "n"(TA), "n"(TB));
}
template<int TA, int TB> __device__ __forceinline__ void wgmma_ss0_n128(float (&d)[64], uint64_t da, uint64_t db) {
  asm volatile("{\n.reg .pred p;\nsetp.ne.b32 p, 0, 0;\n"
    "wgmma.mma_async.sync.aligned.m64n128k16.f32.bf16.bf16 {%0, %1, %2, %3, %4, %5, %6, %7, %8, %9, %10, %11, %12, %13, %14, %15, %16, %17, %18, %19, %20, %21, %22, %23, %24, %25, %26, %27, %28, %29, %30, %31, %32, %33, %34, %35, %36, %37, %38, %39, %40, %41, %42, %43, %44, %45, %46, %47, %48, %49, %50, %51, %52, %53, %54, %55, %56, %57, %58, %59, %60, %61, %62, %63}, %64, %65, p, 1, 1, %66, %67;\n}\n"
    : "=f"(d[0]), "=f"(d[1]), "=f"(d[2]), "=f"(d[3]), "=f"(d[4]), "=f"(d[5]), "=f"(d[6]), "=f"(d[7]), "=f"(d[8]), "=f"(d[9]), "=f"(d[10]), "=f"(d[11]), "=f"(d[12]), "=f"(d[13]), "=f"(d[14]), "=f"(d[15]), "=f"(d[16]), "=f"(d[17]), "=f"(d[18]), "=f"(d[19]), "=f"(d[20]), "=f"(d[21]), "=f"(d[22]), "=f"(d[23]), "=f"(d[24]), "=f"(d[25]), "=f"(d[26]), "=f"(d[27]), "=f"(d[28]), "=f"(d[29]), "=f"(d[30]), "=f"(d[31]), "=f"(d[32]), "=f"(d[33]), "=f"(d[34]), "=f"(d[35]), "=f"(d[36]), "=f"(d[37]), "=f"(d[38]), "=f"(d[39]), "=f"(d[40]), "=f"(d[41]), "=f"(d[42]), "=f"(d[43]), "=f"(d[44]), "=f"(d[45]), "=f"(d[46]), "=f"(d[47]), "=f"(d[48]), "=f"(d[49]), "=f"(d[50]), "=f"(d[51]), "=f"(d[52]), "=f"(d[53]), "=f"(d[54]), "=f"(d[55]), "=f"(d[56]), "=f"(d[57]), "=f"(d[58]), "=f"(d[59]), "=f"(d[60]), "=f"(d[61]), "=f"(d[62]), "=f"(d[63])
    : "l"(da), "l"(db), "n"(TA), "n"(TB));
}
template<int N, int TA, int TB> __device__ __forceinline__ void wgmma_ss0(float (&d)[N / 2], uint64_t da, uint64_t db) {
  if constexpr (N == 24) wgmma_ss0_n24<TA, TB>(d, da, db);
  if constexpr (N == 64) wgmma_ss0_n64<TA, TB>(d, da, db);
  if constexpr (N == 112) wgmma_ss0_n112<TA, TB>(d, da, db);
  if constexpr (N == 128) wgmma_ss0_n128<TA, TB>(d, da, db);
}
template<int N, int TA, int TB> __device__ __forceinline__ void wgmma_ss(float (&d)[N / 2], uint64_t da, uint64_t db, int scale_d) {
  if constexpr (N == 24) wgmma_ss_n24<TA, TB>(d, da, db, scale_d);
  if constexpr (N == 64) wgmma_ss_n64<TA, TB>(d, da, db, scale_d);
  if constexpr (N == 112) wgmma_ss_n112<TA, TB>(d, da, db, scale_d);
  if constexpr (N == 128) wgmma_ss_n128<TA, TB>(d, da, db, scale_d);
}

namespace {

constexpr int SEQ = 2048, DM = 512, FH = 896;
constexpr int NTHREADS = 384;
constexpr int O_STEP = 12;
constexpr int KV_CHAINS = 2;
constexpr int Z2_ROWS = ZR;
constexpr uint32_t STATS_DELAY = 750;

constexpr uint32_t SM_X     = 0;
constexpr uint32_t SM_W     = 131072;
constexpr uint32_t SM_R     = 196608;
constexpr uint32_t SM_MISC  = 229376;
constexpr uint32_t SLOT2    = 30720;
constexpr int      NSLOT2   = 5;
constexpr uint32_t SM_OST   = SM_R;
constexpr uint32_t SLOT3    = 24576;
constexpr uint32_t SM_BAR   = SM_MISC;
constexpr uint32_t SM_G     = SM_MISC + 512;
constexpr uint32_t SM_KVS   = SM_MISC + 1024;
constexpr uint32_t SM_KVSUM = SM_R + 28672;
constexpr uint32_t SM_Z1X   = SM_R + 16384;
constexpr uint32_t SM_KVB   = SM_R + 16384;
constexpr uint32_t SM_TOTAL = 232448;
enum { B_XFULL = 0, B_W1FULL = 8  , B_P2FULL = 16, B_KVFREE = 22, B_Z1F = 23, B_ORDER = 24, B_HOK1 = 25,
       B_Z2 = 26, B_RFREE1 = 27, B_BSP = 28, B_O = 29, B_H0 = 30, B_H1 = 31, B_KV = 32, B_GATE = 33, B_Z1 = 34,
       B_KVRED = 39, B_Z2OK = 40, B_OOK = 41, B_HOK = 42, B_O2 = 43, B_P3FULL = 44, B_P3EMPTY = 52, B_WB2 = 61, B_WB0 = 62, B_WB1 = 63,
       B_HFULL = 192, B_HEMPTY = 197, B_P2EMPTY = 202, B_W1FULLB = 208  , B_W1EMPTY = 214   };

__device__ __align__(1024) __nv_bfloat16 g_z2T[FH * SEQ];
__device__ __align__(1024) __nv_bfloat16 g_O[SEQ * DM];
__device__ __align__(1024) __nv_bfloat16 g_H[SEQ * FH];
__device__ __align__(128) float g_kv[8][1088];
__device__ __align__(128) unsigned long long g_stats[16][8][128];
__device__ __align__(128) unsigned long long g_gate[SEQ];
enum { RB_O = 8, RB_H = 9, RB_H2 = 10,
       SL_Z2 = 16, SL_KV = 17, SL_ZERO = 18 };
__device__ __align__(128) unsigned int g_rb[16][32];
__device__ __align__(128) unsigned int g_sl[8][32];
__device__ unsigned int g_spare[4];
#define TR(i) do { } while (0)
#define TR2(i) do { } while (0)
#define SPIN_LIMIT (1u << 20)
#define TIMEOUT(code) { __trap(); }

__device__ __forceinline__ uint32_t clock32() { uint32_t c; asm volatile("mov.u32 %0, %%clock;" : "=r"(c)); return c; }
__device__ __forceinline__ uint32_t smem_u32(const void* p) { return (uint32_t)__cvta_generic_to_shared(p); }
__device__ __forceinline__ void mbar_init(uint32_t bar, uint32_t cnt) { asm volatile("mbarrier.init.shared::cta.b64 [%0], %1;" :: "r"(bar), "r"(cnt) : "memory"); }
__device__ __forceinline__ void mbar_expect_tx(uint32_t bar, uint32_t bytes) { asm volatile("mbarrier.arrive.expect_tx.shared::cta.b64 _, [%0], %1;" :: "r"(bar), "r"(bytes) : "memory"); }
__device__ __forceinline__ void mbar_arrive(uint32_t bar) { asm volatile("mbarrier.arrive.shared::cta.b64 _, [%0];" :: "r"(bar) : "memory"); }
__device__ __forceinline__ bool mbar_try(uint32_t bar, uint32_t parity) {
  uint32_t ok;
  asm volatile("{\n.reg .pred p;\nmbarrier.try_wait.parity.shared::cta.b64 p, [%1], %2;\nselp.u32 %0, 1, 0, p;\n}\n" : "=r"(ok) : "r"(bar), "r"(parity) : "memory");
  return ok;
}
__device__ __forceinline__ bool mbar_test(uint32_t bar, uint32_t parity) {
  uint32_t ok;
  asm volatile("{\n.reg .pred p;\nmbarrier.test_wait.parity.shared::cta.b64 p, [%1], %2;\nselp.u32 %0, 1, 0, p;\n}\n" : "=r"(ok) : "r"(bar), "r"(parity) : "memory");
  return ok;
}
__device__ __forceinline__ int slot3(int m) { return m == 0 ? 7 : m < 5 ? m + 2 : m - 5; }
__device__ __forceinline__ uint32_t wout_off(int n) { return n < 9 ? slot3(n / 3) * SLOT3 + (n % 3) * 8192 : slot3(n - 6) * SLOT3 + 16384; }
__device__ __forceinline__ uint32_t hslot_off(int a) { return slot3(3 + a) * SLOT3; }
__device__ __forceinline__ void mbar_wait(uint32_t bar, uint32_t parity) {
  uint32_t it = 0;
  while (!mbar_try(bar, parity)) { if (++it > (SPIN_LIMIT >> 4)) TIMEOUT(1000 + ((bar >> 3) & 63)) }
}
__device__ __forceinline__ void tma2d(uint32_t dst, const CUtensorMap* tm, int c0, int c1, uint32_t bar) {
  asm volatile("cp.async.bulk.tensor.2d.shared::cluster.global.mbarrier::complete_tx::bytes [%0], [%1, {%3, %4}], [%2];"
    :: "r"(dst), "l"(tm), "r"(bar), "r"(c0), "r"(c1) : "memory");
}
__device__ __forceinline__ void tma4d(uint32_t dst, const CUtensorMap* tm, int c0, int c1, int c2, int c3, uint32_t bar) {
  asm volatile("cp.async.bulk.tensor.4d.shared::cluster.global.mbarrier::complete_tx::bytes [%0], [%1, {%3, %4, %5, %6}], [%2];"
    :: "r"(dst), "l"(tm), "r"(bar), "r"(c0), "r"(c1), "r"(c2), "r"(c3) : "memory");
}
__device__ __forceinline__ void tma_store2d(const CUtensorMap* tm, uint32_t src, int c0, int c1) {
  asm volatile("cp.async.bulk.tensor.2d.global.shared::cta.bulk_group [%0, {%2, %3}], [%1];"
    :: "l"(tm), "r"(src), "r"(c0), "r"(c1) : "memory");
}
__device__ __forceinline__ void tma_store3d(const CUtensorMap* tm, uint32_t src, int c0, int c1, int c2) {
  asm volatile("cp.async.bulk.tensor.3d.global.shared::cta.bulk_group [%0, {%2, %3, %4}], [%1];"
    :: "l"(tm), "r"(src), "r"(c0), "r"(c1), "r"(c2) : "memory");
}
__device__ __forceinline__ void bulk_commit() { asm volatile("cp.async.bulk.commit_group;" ::: "memory"); }
__device__ __forceinline__ void bulk_wait_read() { asm volatile("cp.async.bulk.wait_group.read 0;" ::: "memory"); }
__device__ __forceinline__ void bulk_wait_all() { asm volatile("cp.async.bulk.wait_group 0;" ::: "memory"); }
__device__ __forceinline__ void l2_prefetch(const void* p, uint32_t bytes, int lane) {
  for (uint32_t o = lane * 128; o < bytes; o += 4096) asm volatile("prefetch.global.L2 [%0];" :: "l"((const char*)p + o) : "memory");
}
__device__ __forceinline__ void prefetch_tmap(const CUtensorMap* tm) { asm volatile("prefetch.tensormap [%0];" :: "l"(tm) : "memory"); }
__device__ __forceinline__ void fence_async_smem() { asm volatile("fence.proxy.async.shared::cta;" ::: "memory"); }
__device__ __forceinline__ void fence_async_global() { asm volatile("fence.proxy.async.global;" ::: "memory"); }
__device__ __forceinline__ void wgmma_fence() { asm volatile("wgmma.fence.sync.aligned;" ::: "memory"); }
__device__ __forceinline__ void wgmma_commit() { asm volatile("wgmma.commit_group.sync.aligned;" ::: "memory"); }
template<int N> __device__ __forceinline__ void wgmma_wait() { asm volatile("wgmma.wait_group.sync.aligned %0;" :: "n"(N) : "memory"); }
__device__ __forceinline__ uint64_t make_desc(uint32_t addr, uint32_t lbo, uint32_t sbo, uint32_t swz) {
  return (uint64_t)((addr & 0x3FFFF) >> 4) | ((uint64_t)(lbo >> 4) << 16) | ((uint64_t)(sbo >> 4) << 32) | ((uint64_t)swz << 62);
}
__device__ __forceinline__ uint32_t pack2(float lo, float hi) { uint32_t r; asm("cvt.rn.bf16x2.f32 %0, %1, %2;" : "=r"(r) : "f"(hi), "f"(lo)); return r; }
__device__ __forceinline__ uint32_t fma_bf2(uint32_t a, uint32_t b, uint32_t c) { uint32_t r; asm("fma.rn.bf16x2 %0, %1, %2, %3;" : "=r"(r) : "r"(a), "r"(b), "r"(c)); return r; }
__device__ __forceinline__ uint32_t mul_bf2(uint32_t a, uint32_t b) { uint32_t r; asm("mul.rn.bf16x2 %0, %1, %2;" : "=r"(r) : "r"(a), "r"(b)); return r; }
__device__ __forceinline__ float bf_lo(uint32_t v) { return __uint_as_float(v << 16); }
__device__ __forceinline__ float bf_hi(uint32_t v) { return __uint_as_float(v & 0xffff0000u); }
__device__ __forceinline__ void stsm4(uint32_t a, uint32_t r0, uint32_t r1, uint32_t r2, uint32_t r3) {
  asm volatile("stmatrix.sync.aligned.m8n8.x4.shared.b16 [%0], {%1, %2, %3, %4};" :: "r"(a), "r"(r0), "r"(r1), "r"(r2), "r"(r3) : "memory");
}
__device__ __forceinline__ void stsm4t(uint32_t a, uint32_t r0, uint32_t r1, uint32_t r2, uint32_t r3) {
  asm volatile("stmatrix.sync.aligned.m8n8.x4.trans.shared.b16 [%0], {%1, %2, %3, %4};" :: "r"(a), "r"(r0), "r"(r1), "r"(r2), "r"(r3) : "memory");
}
__device__ __forceinline__ void mma16816_acc(float (&c)[4], uint32_t a0, uint32_t a1, uint32_t a2, uint32_t a3, uint32_t b0, uint32_t b1) {
  asm volatile("mma.sync.aligned.m16n8k16.row.col.f32.bf16.bf16.f32 {%0, %1, %2, %3}, {%4, %5, %6, %7}, {%8, %9}, {%0, %1, %2, %3};"
    : "+f"(c[0]), "+f"(c[1]), "+f"(c[2]), "+f"(c[3]) : "r"(a0), "r"(a1), "r"(a2), "r"(a3), "r"(b0), "r"(b1));
}
__device__ __forceinline__ void publish_bulk(unsigned int* p) {
  asm volatile("fence.proxy.async.global;" ::: "memory");
  asm volatile("red.relaxed.gpu.global.add.u32 [%0], 1;" :: "l"(p) : "memory");
}
__device__ __forceinline__ uint32_t ld_relaxed(const unsigned int* p) { uint32_t v; asm volatile("ld.relaxed.gpu.global.u32 %0, [%1];" : "=r"(v) : "l"(p) : "memory"); return v; }
template<int SLEEP> __device__ __forceinline__ void wait_flag(const unsigned int* p, uint32_t target) {
  uint32_t it = 0;
  while ((int)(ld_relaxed(p) - target) < 0) { if (SLEEP) __nanosleep(SLEEP); if (++it > SPIN_LIMIT) TIMEOUT(2000 + (int)target) }
  asm volatile("fence.acquire.gpu;" ::: "memory");
}
__device__ __forceinline__ void publish_and_wait(unsigned int* p, uint32_t target) {
  uint32_t v, it = 0;
  asm volatile("fence.proxy.async.global;" ::: "memory");
  asm volatile("atom.relaxed.gpu.global.add.u32 %0, [%1], 1;" : "=r"(v) : "l"(p) : "memory");
  v += 1;
  while ((int)(v - target) < 0) { v = ld_relaxed(p); if (++it > SPIN_LIMIT) TIMEOUT(2999) }
  asm volatile("fence.acquire.gpu;" ::: "memory");
}
__device__ __forceinline__ float gelu_f(float x) {
  float u = x * fmaf(x * x, 0.0356774081f, 0.7978845608f);
  float t; asm("tanh.approx.f32 %0, %1;" : "=f"(t) : "f"(u));
  return fmaf(x, t, x);
}
__device__ __forceinline__ float phi_f(float t) {
  float e; asm("ex2.approx.ftz.f32 %0, %1;" : "=f"(e) : "f"(t * 1.4426950409f));
  return (t > 0.f ? t + 1.f : e) + 1e-6f;
}

struct Params {
  CUtensorMap x, win, win2, wqkv, wsp, z2, z2s, o, os, hst, hst2, hld, wo, wout;
  const __nv_bfloat16 *p_x, *p_wqkv, *p_win, *p_wsp, *p_wo, *p_wout, *p_bsp, *p_gw;
  __nv_bfloat16* p_out;
};

__device__ __forceinline__ int work_from_smid(uint32_t smid) {
  const int t = smid >> 1, u = t - 32, q7 = (u * 37) >> 8;
  const int g = t < 32 ? (t & 7) : t < 60 ? 1 + u - 7 * q7 : 0;
  const int slot = t < 32 ? (t >> 3) : t < 60 ? 4 + q7 : t - 58;
  const int l = slot * 2 + (smid & 1);
  const int w = ((g >> 1) * 4 + (l >> 2)) * 8 + (g & 1) * 4 + (l & 3);
  return (t == 60 || t == 61) ? -1 : w;
}

__device__ __forceinline__ int w_slot(int n) { return n < 6 ? n : n < 12 ? n - 6 : n & 3; }
__device__ __forceinline__ uint32_t w_full_parity(int n) {
  return n < 8 ? n >= 6 : n < 16 ? n >= 14 : n < 24 ? ((n >> 2) ^ (n >> 1)) & 1 : n < 26;
}

template<int N, bool FIRST>
__device__ __forceinline__ void p1_step(float (&a0)[N / 2], float (&a1)[N / 2], uint32_t sb, int c, int n0, bool wait_x, bool leader) {
  const uint32_t bar = sb + SM_BAR;
  const int slot = w_slot(n0 + c);
  if (wait_x) mbar_wait(bar + 8 * (B_XFULL + c), 0);
  mbar_wait(bar + 8 * (B_W1FULL + slot), w_full_parity(n0 + c));
  if (TRACE2 && leader) TR2(32 + n0 + c);
  const uint64_t da = make_desc(sb + SM_X, 16, 1024, 1) + c * 1024, db = make_desc(sb + SM_W, 8192, 1024, 1) + slot * 1024;
  wgmma_fence();
#pragma unroll
  for (int k = 0; k < 4; k++) {
    if (FIRST && k == 0) { wgmma_ss0<N, 0, 1>(a0, da, db); wgmma_ss0<N, 0, 1>(a1, da + 512, db); }
    else { wgmma_ss<N, 0, 1>(a0, da + 2 * k, db + 128 * k, 1); wgmma_ss<N, 0, 1>(a1, da + 512 + 2 * k, db + 128 * k, 1); }
  }
  wgmma_commit();
}
template<int N>
__device__ __forceinline__ void p1_rest(float (&a0)[N / 2], float (&a1)[N / 2], uint32_t sb, int n0, bool wait_x, bool leader) {
  const uint32_t bar = sb + SM_BAR;
#pragma unroll 1
  for (int c = 1; c < 8; c++) {
    p1_step<N, false>(a0, a1, sb, c, n0, wait_x, leader);
    if (n0 == 0 && c == 7 && leader) mbar_arrive(bar + 8 * B_ORDER);
    wgmma_wait<1>();
    if (leader) mbar_arrive(bar + 8 * (B_W1EMPTY + w_slot(n0 + c - 1)));
  }
  wgmma_wait<0>();
  if (leader) mbar_arrive(bar + 8 * (B_W1EMPTY + w_slot(n0 + 7)));
}

__device__ __forceinline__ void phi_pass(uint32_t sb, int half, int lane) {
  const uint32_t bar = sb + SM_BAR;
  mbar_wait(bar + 8 * B_O, 0);
#pragma unroll 2
  for (int i = 0; i < 16; i++) {
    const uint32_t a = sb + SM_OST + half * 8192 + i * 512 + lane * 16;
    uint32_t x, y, z, w;
    asm volatile("ld.shared.v4.u32 {%0, %1, %2, %3}, [%4];" : "=r"(x), "=r"(y), "=r"(z), "=r"(w) : "r"(a) : "memory");
    x = pack2(phi_f(bf_lo(x)), phi_f(bf_hi(x))); y = pack2(phi_f(bf_lo(y)), phi_f(bf_hi(y)));
    z = pack2(phi_f(bf_lo(z)), phi_f(bf_hi(z))); w = pack2(phi_f(bf_lo(w)), phi_f(bf_hi(w)));
    asm volatile("st.shared.v4.u32 [%0], {%1, %2, %3, %4};" :: "r"(a), "r"(x), "r"(y), "r"(z), "r"(w) : "memory");
  }
  fence_async_smem();
  __syncwarp();
  if (lane == 0) mbar_arrive(bar + 8 * B_KV);
}

__device__ __forceinline__ void gate16(const __nv_bfloat16* x, const __nv_bfloat16* gw, int row0, uint32_t tag, int lane) {
        {
          const uint4 w0 = __ldg(reinterpret_cast<const uint4*>(gw + lane * 8)), w1 = __ldg(reinterpret_cast<const uint4*>(gw + 256 + lane * 8));
          const __nv_bfloat16* xr = x + (size_t)row0 * DM + lane * 8;
          float p[16];
#pragma unroll
          for (int r0 = 0; r0 < 16; r0 += 8) {
            uint4 xa[8], xb[8];
#pragma unroll
            for (int r = 0; r < 8; r++) { xa[r] = __ldg(reinterpret_cast<const uint4*>(xr + (r0 + r) * DM)); xb[r] = __ldg(reinterpret_cast<const uint4*>(xr + (r0 + r) * DM + 256)); }
#pragma unroll
            for (int r = 0; r < 8; r++) {
              float t = bf_lo(xa[r].x) * bf_lo(w0.x), u = bf_hi(xa[r].x) * bf_hi(w0.x);
              t = fmaf(bf_lo(xa[r].y), bf_lo(w0.y), t); u = fmaf(bf_hi(xa[r].y), bf_hi(w0.y), u);
              t = fmaf(bf_lo(xa[r].z), bf_lo(w0.z), t); u = fmaf(bf_hi(xa[r].z), bf_hi(w0.z), u);
              t = fmaf(bf_lo(xa[r].w), bf_lo(w0.w), t); u = fmaf(bf_hi(xa[r].w), bf_hi(w0.w), u);
              t = fmaf(bf_lo(xb[r].x), bf_lo(w1.x), t); u = fmaf(bf_hi(xb[r].x), bf_hi(w1.x), u);
              t = fmaf(bf_lo(xb[r].y), bf_lo(w1.y), t); u = fmaf(bf_hi(xb[r].y), bf_hi(w1.y), u);
              t = fmaf(bf_lo(xb[r].z), bf_lo(w1.z), t); u = fmaf(bf_hi(xb[r].z), bf_hi(w1.z), u);
              t = fmaf(bf_lo(xb[r].w), bf_lo(w1.w), t); u = fmaf(bf_hi(xb[r].w), bf_hi(w1.w), u);
              p[r0 + r] = t + u;
            }
          }
#define GRED(h) _Pragma("unroll") for (int r = 0; r < (h); r++) p[r] = ((lane & (h)) ? p[r + (h)] : p[r]) + __shfl_xor_sync(0xffffffffu, (lane & (h)) ? p[r] : p[r + (h)], (h));
          GRED(8) GRED(4) GRED(2) GRED(1)
          const float mine = p[0] + __shfl_xor_sync(0xffffffffu, p[0], 16);
          if (lane < 16) {
            const float gv = 1.f / (1.f + __expf(-mine));
            const unsigned long long v = (unsigned long long)__float_as_uint(gv) | ((unsigned long long)tag << 32);
            asm volatile("st.relaxed.gpu.global.u64 [%0], %1;" :: "l"(&g_gate[row0 + lane]), "l"(v) : "memory");
          }
        }
}

template<bool BY_SMID>
__global__ void __launch_bounds__(NTHREADS, 1) fused_kernel(const __grid_constant__ Params P) {
  extern __shared__ __align__(1024) uint8_t smem[];
  constexpr uint32_t sb = 1024;
  const uint32_t bar = sb + SM_BAR;
  const int tid = threadIdx.x, lane = tid & 31;
  const int warp = __shfl_sync(0xffffffffu, tid >> 5, 0);

  uint32_t smid; asm volatile("mov.u32 %0, %%smid;" : "=r"(smid));
  const int work = BY_SMID ? work_from_smid(smid) : (int)blockIdx.x;
  const int rb = work >> 3, sl = work & 7;
  if (warp == 8 && work >= 0) {
    if (lane == 0)
      for (int i = 0; i < 14; i++) mbar_init(bar + 8 * i, 1);
    __syncwarp();
    asm volatile("bar.arrive 4, 384;" ::: "memory");
    if (lane == 0) {
#pragma unroll 1
      for (int n = 0; n < 8; n++) {
        if (n < 6) TR2(n);
        mbar_expect_tx(bar + 8 * (B_XFULL + n), 16384); tma2d(sb + SM_X + n * 16384, &P.x, n * 64, rb * 128, bar + 8 * (B_XFULL + n));
        if (n < 6) {
          const uint32_t fb = bar + 8 * (B_W1FULL + n), dst = sb + SM_W + n * 16384;
          mbar_expect_tx(fb, 16384);
          tma2d(dst, &P.win, FH + sl * 64, n * 64, fb); tma4d(dst + 8192, &P.win2, 0, sl, 1, n * 64, fb);
        }
      }
    }
  }
  if (work < 0) {
    const uint32_t e = ld_relaxed(&g_spare[smid - 120]);
    for (int i = tid; i < 544; i += NTHREADS) reinterpret_cast<float4*>(&g_kv[(smid - 120) * 2][0])[i] = make_float4(0.f, 0.f, 0.f, 0.f);
    __syncthreads();
    if (tid < 2) asm volatile("red.release.gpu.global.add.u32 [%0], 1;" :: "l"(&g_sl[(smid - 120) * 2 + tid][SL_ZERO]) : "memory");
    __nanosleep(3000);
#pragma unroll 1
    for (int b = warp; b < 32; b += 12) gate16(P.p_x, P.p_gw, (smid - 120) * 512 + b * 16, (e + 1) & 1, lane);
    __syncthreads();
    if (tid == 0) {
      for (int j = 0; j < 8; j++) {
        uint32_t it = 0;
        while ((int)(ld_relaxed(&g_sl[j][SL_KV]) - 16 * (e + 1)) < 0) { __nanosleep(500); if (++it > SPIN_LIMIT) TIMEOUT(3000) }
      }
      g_spare[smid - 120] = e + 1;
    }
    return;
  }
  if (tid == 288) {
    if (smem_u32(smem) != sb) __trap();
    for (int i = 0; i < 6; i++) { mbar_init(bar + 8 * (B_W1FULLB + i), 1); mbar_init(bar + 8 * (B_W1EMPTY + i), 1); }
    for (int i = 0; i < NSLOT2; i++) { mbar_init(bar + 8 * (B_P2FULL + i), 1); mbar_init(bar + 8 * (B_P2EMPTY + i), 2); }
    for (int i = 0; i < 8; i++) { mbar_init(bar + 8 * (B_P3FULL + i), 1); mbar_init(bar + 8 * (B_P3EMPTY + i), 2); }
    mbar_init(bar + 8 * B_Z2, 4); mbar_init(bar + 8 * B_RFREE1, 1); mbar_init(bar + 8 * B_BSP, 1); mbar_init(bar + 8 * B_KVFREE, 1); mbar_init(bar + 8 * B_Z1F, 4); mbar_init(bar + 8 * B_ORDER, 1);
    mbar_init(bar + 8 * B_O, 4); mbar_init(bar + 8 * B_H0, 8); mbar_init(bar + 8 * B_H1, 8); mbar_init(bar + 8 * B_HOK1, 1);
    mbar_init(bar + 8 * B_Z2OK, 1); mbar_init(bar + 8 * B_OOK, 1); mbar_init(bar + 8 * B_HOK, 1);
    mbar_init(bar + 8 * B_KV, 3); mbar_init(bar + 8 * B_O2, 8); mbar_init(bar + 8 * B_GATE, 1); mbar_init(bar + 8 * B_Z1, 4);
    mbar_init(bar + 8 * B_WB2, 1); mbar_init(bar + 8 * B_WB0, 1); mbar_init(bar + 8 * B_WB1, 1);
    for (int i = 0; i < 5; i++) { mbar_init(bar + 8 * (B_HFULL + i), 1); mbar_init(bar + 8 * (B_HEMPTY + i), 2); } mbar_init(bar + 8 * B_KVRED, 4);
    fence_async_smem();
  }
  __syncwarp();
  if (warp == 9) asm volatile("bar.arrive 5, 64;" ::: "memory");

  if (warp >= 8) {
    if (warp == 8) {
      asm volatile("bar.sync 5, 64;" ::: "memory");
      if (lane == 0) {
#pragma unroll 1
        for (int n = 6; n < 24; n++) {
          const int slot = w_slot(n), c = n & 7, t = n >> 3;
          mbar_wait(bar + 8 * (B_W1EMPTY + slot), n < 12 ? 0 : (n >> 2) & 1);
          const uint32_t fb = bar + 8 * ((t == 1 ? B_W1FULLB : B_W1FULL) + slot), dst = sb + SM_W + slot * 16384;
          TR2(n);
          mbar_expect_tx(fb, 16384);
          if (t == 1) { tma2d(dst, &P.wqkv, 512 + sl * 64, c * 64, fb); tma2d(dst + 8192, &P.wqkv, 1024 + sl * 64, c * 64, fb); }
          else { tma2d(dst, &P.win, (t == 0 ? FH : 0) + sl * 64, c * 64, fb); tma4d(dst + 8192, &P.win2, 0, sl, t == 0, c * 64, fb); }
        }
#pragma unroll 1
        for (int n = 24; n < 28; n++) {
          const int slot = n & 3;
          mbar_wait(bar + 8 * (B_W1EMPTY + slot), 0);
          const uint32_t fb = bar + 8 * (B_W1FULLB + slot), dst = sb + SM_W + slot * 16384;
          mbar_expect_tx(fb, 16384);
          tma2d(dst, &P.wqkv, sl * 64, (n - 24) * 128, fb); tma2d(dst + 8192, &P.wqkv, sl * 64, (n - 24) * 128 + 64, fb);
          if (n == 24) { prefetch_tmap(&P.wsp); prefetch_tmap(&P.z2); }
        }
        TR(40);
      }
      int s = 0; uint32_t ph = 0;
      if (lane == 0) {
        mbar_wait(bar + 8 * B_Z2OK, 0);
        fence_async_global();
        TR(41);
#pragma unroll 1
        for (int n = 0; n < 32; n++) {
          mbar_wait(bar + 8 * (B_P2EMPTY + s), ph);
          const uint32_t fb = bar + 8 * (B_P2FULL + s), dst = sb + s * SLOT2;
          TR2(64 + n);
          mbar_expect_tx(fb, SLOT2);
          tma2d(dst, &P.wsp, n * 64, rb * 128, fb);
          tma2d(dst + 16384, &P.z2, n * 64, sl * 112, fb);
          if (n == 0) TR(42);
          if (++s == NSLOT2) { s = 0; ph ^= 1; }
        }
        mbar_wait(bar + 8 * B_OOK, 0);
        fence_async_global();
#pragma unroll
        for (int m = 0; m < 8; m++) {
          if (m == 1) { mbar_wait(bar + 8 * (B_P2EMPTY + 2), 0); mbar_wait(bar + 8 * (B_P2EMPTY + 3), 0); }
          if (m == 3) mbar_wait(bar + 8 * (B_P2EMPTY + 4), 0);
          if (m == 5) mbar_wait(bar + 8 * (B_P2EMPTY + 0), 1);
          if (m == 6) mbar_wait(bar + 8 * (B_P2EMPTY + 1), 1);
          const uint32_t fb = bar + 8 * (B_P3FULL + m), dst = sb + slot3(m) * SLOT3;
          mbar_expect_tx(fb, SLOT3);
          tma2d(dst, &P.o, m * 64, rb * 128, fb);
          tma2d(dst + 16384, &P.wo, sl * 64, m * 64, fb);
        }
        mbar_expect_tx(bar + 8 * B_WB2, 8192); mbar_expect_tx(bar + 8 * B_WB0, 8 * 8192); mbar_expect_tx(bar + 8 * B_WB1, 5 * 8192);
#pragma unroll
        for (int n = 0; n < 9; n++) {
          if (n % 3 == 0) mbar_wait(bar + 8 * (B_P3EMPTY + n / 3), 0);
          tma2d(sb + wout_off(n), &P.wout, sl * 64, (n == 0 ? sl : n - (n <= sl)) * 64, bar + 8 * (n == 0 ? B_WB2 : B_WB0));
        }
        int wdone = 0;
#pragma unroll 1
        while (wdone < 5 && !mbar_test(bar + 8 * B_HOK, 0)) {
          mbar_wait(bar + 8 * (B_P3EMPTY + 3 + wdone), 0);
          tma2d(sb + hslot_off(wdone) + 16384, &P.wout, sl * 64, (9 + wdone) * 64, bar + 8 * B_WB1);
          wdone++;
        }
        mbar_wait(bar + 8 * B_HOK, 0);
        fence_async_global();
        TR(43);
#pragma unroll
        for (int n = 0; n < 13; n++) {
          if (n == 7) { mbar_wait(bar + 8 * B_HOK1, 0); fence_async_global(); }
          if (n >= 5) mbar_wait(bar + 8 * (B_HEMPTY + n % 5), (n / 5 - 1) & 1);
          else mbar_wait(bar + 8 * (B_P3EMPTY + 3 + n), 0);
          TR2(160 + n);
          mbar_expect_tx(bar + 8 * (B_HFULL + n % 5), 16384);
          tma2d(sb + hslot_off(n % 5), &P.hld, (n + (n >= sl)) * 64, rb * 128, bar + 8 * (B_HFULL + n % 5));
          if (n == 4) {
#pragma unroll 1
            for (; wdone < 5; wdone++) tma2d(sb + hslot_off(wdone) + 16384, &P.wout, sl * 64, (9 + wdone) * 64, bar + 8 * B_WB1);
          }
        }
        TR(44);
      }
    } else if (warp == 9) {
      asm volatile("bar.sync 4, 384;" ::: "memory");
      const uint32_t epoch = ld_relaxed(&g_sl[sl][rb]);
      if (!BY_SMID && rb == 0) {
        if (lane < 16) asm volatile("st.shared.v4.u32 [%0], {%1, %1, %1, %1};" :: "r"(sb + SM_KVS + 1024 + lane * 16), "r"(0) : "memory");
        fence_async_smem();
        __syncwarp();
      }
      if (lane == 0) {
        mbar_wait(bar + 8 * B_XFULL, 0);
        TR(58);
        if (!BY_SMID && rb == 0) {
          for (int i = 0; i < 17; i++) asm volatile("cp.async.bulk.global.shared::cta.bulk_group [%0], [%1], %2;" :: "l"(&g_kv[sl][i * 64]), "r"(sb + SM_KVS + 1024), "r"(256) : "memory");
          bulk_commit(); bulk_wait_all(); publish_bulk(&g_sl[sl][SL_ZERO]);
        }
        prefetch_tmap(&P.wqkv); prefetch_tmap(&P.z2); prefetch_tmap(&P.z2s); prefetch_tmap(&P.wsp); prefetch_tmap(&P.o); prefetch_tmap(&P.os); prefetch_tmap(&P.hst);
        prefetch_tmap(&P.hld); prefetch_tmap(&P.wo); prefetch_tmap(&P.wout);
        mbar_wait(bar + 8 * B_Z2, 0);
        TR(50);
#pragma unroll 1
        for (int i = 0; i < 224 / Z2_ROWS; i++) {
          const int r = i * Z2_ROWS;
          tma_store2d(&P.z2s, sb + SM_R + r * 128, rb * 128 + (r >= 112 ? 64 : 0), sl * 112 + (r >= 112 ? r - 112 : r));
          bulk_commit();
          asm volatile("cp.async.bulk.wait_group.read %0;" :: "n"(ZP) : "memory");
        }
        bulk_wait_all();
        TR(52);
        mbar_arrive(bar + 8 * B_RFREE1);
        publish_bulk(&g_sl[sl][SL_Z2]);
        TR(45);
        wait_flag<100>(&g_sl[sl][SL_ZERO], epoch + 1);
        fence_async_global();
        mbar_wait(bar + 8 * B_KVRED, 0);
        asm volatile("cp.reduce.async.bulk.global.shared::cta.bulk_group.add.f32 [%0], [%1], %2;" :: "l"(&g_kv[sl][0]), "r"(sb + SM_KVSUM), "r"(4096) : "memory");
        asm volatile("cp.reduce.async.bulk.global.shared::cta.bulk_group.add.f32 [%0], [%1], %2;" :: "l"(&g_kv[sl][1024]), "r"(sb + SM_KVS + 1024), "r"(256) : "memory");
        bulk_commit();
        bulk_wait_all();
        mbar_arrive(bar + 8 * B_KVFREE);
        publish_bulk(&g_sl[sl][SL_KV]);
        TR(13);
      }
      __syncwarp();
      phi_pass(sb, 0, lane);
      if (lane == 0) {
        TR(59);
        mbar_wait(bar + 8 * B_O2, 0);
#pragma unroll 1
        for (int i = 0; i < 4; i++) { tma_store2d(&P.os, sb + SM_OST + i * 4096, sl * 64, rb * 128 + i * 32); bulk_commit(); bulk_wait_read(); }
        bulk_wait_all();
        publish_bulk(&g_rb[rb][RB_O]);
        TR(46);
        prefetch_tmap(&P.hst); prefetch_tmap(&P.hst2);
        mbar_wait(bar + 8 * B_H0, 0);
        tma_store2d(&P.hst, sb + SM_R, sl * 64, rb * 128);
        bulk_commit();
        bulk_wait_all();
        mbar_wait(bar + 8 * B_H1, 0);
        tma_store3d(&P.hst2, sb + SM_R + 16384, 0, sl, rb * 128);
        bulk_commit();
        TR(53);
        publish_and_wait(&g_rb[rb][RB_H], 8 * (epoch + 1));
        mbar_arrive(bar + 8 * B_HOK);
        TR(56);
        bulk_wait_all();
        publish_and_wait(&g_rb[rb][RB_H2], 8 * (epoch + 1));
        mbar_arrive(bar + 8 * B_HOK1);
        TR(15);
      }
    } else {
      asm volatile("bar.sync 4, 384;" ::: "memory");
      const uint32_t epoch = ld_relaxed(&g_sl[sl][rb]);
      const uint32_t tag = (epoch + 1) & 1;
      if (warp == 11) {
        mbar_wait(bar + 8 * (B_XFULL + 7), 0);
        const uint2 bv = __ldg(reinterpret_cast<const uint2*>(P.p_bsp + rb * 128) + lane);
        { const char* a = (const char*)(P.p_wqkv + (size_t)(work * 4 + (lane >> 4)) * 1536 + 512) + (lane & 15) * 128;
          asm volatile("prefetch.global.L2 [%0];" :: "l"(a) : "memory"); asm volatile("prefetch.global.L2 [%0];" :: "l"(a + 2 * 3072) : "memory"); }
        if (lane < 28) { const char* a = (const char*)(P.p_win + (size_t)(work * 4 + (lane >= 14 ? 1 : 0)) * 1792) + (lane % 14) * 128;
          asm volatile("prefetch.global.L2 [%0];" :: "l"(a) : "memory"); asm volatile("prefetch.global.L2 [%0];" :: "l"(a + 2 * 3584) : "memory"); }
        asm volatile("prefetch.global.L2 [%0];" :: "l"((const char*)(P.p_wqkv + (size_t)(work * 4 + (lane >> 3)) * 1536) + (lane & 7) * 128) : "memory");
        reinterpret_cast<float4*>(smem + SM_KVS)[lane] = make_float4(bf_lo(bv.x), bf_hi(bv.x), bf_lo(bv.y), bf_hi(bv.y));
        __syncwarp();
        if (lane == 0) mbar_arrive(bar + 8 * B_BSP);
        const __nv_bfloat16* w = P.p_wsp + (size_t)work * 16 * 2048;
#pragma unroll 1
        for (int i = 0; i < 16; i++) {
          asm volatile("{\n.reg .pred p;\nmbarrier.try_wait.parity.shared::cta.b64 p, [%0], %1, %2;\n}" :: "r"(bar + 8 * ((i < 8 ? B_W1FULLB : B_W1FULL) + w_slot(8 + i))), "r"(w_full_parity(8 + i)), "r"(1000) : "memory");
          l2_prefetch(w + i * 2048, 4096, lane);
        }
        l2_prefetch(P.p_wo + (size_t)work * 4 * 512, 4096, lane);
        l2_prefetch(P.p_wout + (size_t)work * 7 * 512, 7168, lane);
        if (lane == 0) TR(49);
        phi_pass(sb, 1, lane);
        if (!BY_SMID) gate16(P.p_x, P.p_gw, rb * 128 + sl * 16, tag, lane);
        if (lane == 0) TR(9);
      } else {
        mbar_wait(bar + 8 * B_RFREE1, 0);
        if (lane == 0) wait_flag<0>(&g_sl[sl][SL_Z2], 16 * (epoch + 1));
        __syncwarp();
        if (lane == 0) { mbar_arrive(bar + 8 * B_Z2OK); TR(55);
          wait_flag<0>(&g_sl[sl][SL_KV], 16 * (epoch + 1)); }
        __syncwarp();
        const float4* src = reinterpret_cast<const float4*>(&g_kv[sl][0]);
        float4 v[8];
#pragma unroll
        for (int i = 0; i < 8; i++) v[i] = __ldcg(src + i * 32 + lane);
        const float za = __ldcg(&g_kv[sl][1024 + lane]), zb = __ldcg(&g_kv[sl][1056 + lane]);
        mbar_wait(bar + 8 * B_Z1F, 0);
#pragma unroll
        for (int i = 0; i < 8; i++) {
          const int idx = i * 32 + lane, h = idx >> 6, d = (idx >> 2) & 15, e = (idx & 3) * 4;
          asm volatile("st.shared.v2.u32 [%0], {%1, %2};" :: "r"(sb + SM_KVB + h * 768 + (e >> 3) * 256 + d * 16 + (e & 7) * 2), "r"(pack2(v[i].x, v[i].y)), "r"(pack2(v[i].z, v[i].w)) : "memory");
        }
        asm volatile("st.shared.v4.u32 [%0], {%1, %1, %1, %1};" :: "r"(sb + SM_KVB + (lane >> 4) * 768 + 512 + (lane & 15) * 16), "r"(pack2(za, za)) : "memory");
        asm volatile("st.shared.v4.u32 [%0], {%1, %1, %1, %1};" :: "r"(sb + SM_KVB + (2 + (lane >> 4)) * 768 + 512 + (lane & 15) * 16), "r"(pack2(zb, zb)) : "memory");
        fence_async_smem();
        __syncwarp();
        if (lane == 0) { mbar_arrive(bar + 8 * B_KV); TR(48); }
        if (lane == 0) {
          mbar_wait(bar + 8 * B_O2, 0);
          wait_flag<0>(&g_rb[rb][RB_O], 8 * (epoch + 1));
          mbar_arrive(bar + 8 * B_OOK);
        }
        __syncwarp();
#pragma unroll
        for (int i = 0; i < 4; i++) {
          unsigned long long v; uint32_t it = 0;
          do { asm volatile("ld.relaxed.gpu.global.u64 %0, [%1];" : "=l"(v) : "l"(&g_gate[rb * 128 + i * 32 + lane]) : "memory"); if (++it > SPIN_LIMIT) TIMEOUT(3004) } while ((uint32_t)(v >> 32) != tag);
          reinterpret_cast<float*>(smem + SM_G)[i * 32 + lane] = __uint_as_float((uint32_t)v);
        }
        __syncwarp();
        if (lane == 0) mbar_arrive(bar + 8 * B_GATE);
      }
    }
  } else {
    asm volatile("bar.sync 4, 384;" ::: "memory");
    const uint32_t epoch = ld_relaxed(&g_rb[rb][sl]);
    const int wg = warp >> 2, w4 = warp & 3;
    const int g = lane >> 2, cq = lane & 3;
    const bool leader = (tid & 127) == 0;
    const int mi = lane >> 3, ri = lane & 7;
    const int mrow = w4 * 16 + (mi & 1) * 8 + ri;
    const int mcol = mi >> 1;

    int s = 0, sp = 0; uint32_t ph = 0;
    const uint64_t dA2 = make_desc(sb + wg * 8192, 16, 1024, 1), dB2 = make_desc(sb + 16384, 16, 1024, 1);
    float acc[56];
    uint32_t zf[28];
    const int row0 = wg * 64 + w4 * 16 + g;
#define P2_INIT() \
        { mbar_wait(bar + 8 * B_BSP, 0); \
          const float bs0 = reinterpret_cast<const float*>(smem + SM_KVS)[row0], bs1 = reinterpret_cast<const float*>(smem + SM_KVS)[row0 + 8]; \
          _Pragma("unroll") for (int i = 0; i < 56; i++) acc[i] = (i & 2) ? bs1 : bs0; }
#define P2_ISSUE(n) \
        mbar_wait(bar + 8 * (B_P2FULL + s), ph); \
        if ((n) == 0 && leader) TR(20 + wg); \
        if (TRACE2 && leader) TR2(96 + 32 * wg + (n)); \
        { const uint64_t da = dA2 + s * (SLOT2 >> 4), db = dB2 + s * (SLOT2 >> 4); \
          wgmma_fence(); \
          _Pragma("unroll") for (int k = 0; k < 4; k++) wgmma_ss<112, 0, 0>(acc, da + 2 * k, db + 2 * k, 1); \
          wgmma_commit(); }
#define P2_RETIRE(n) \
        wgmma_wait<1>(); \
        if ((n) > 0 && leader) mbar_arrive(bar + 8 * (B_P2EMPTY + sp)); \
        sp = s; \
        if (++s == NSLOT2) { s = 0; ph ^= 1; }
    if (wg == 0) {
      {
        float a0[56], a1[56];
        p1_step<112, true>(a0, a1, sb, 0, 0, true, leader);
        p1_rest<112>(a0, a1, sb, 0, true, leader);
        if (leader) TR(1);
        float s0 = 0.f, s1 = 0.f, s2 = 0.f, s3 = 0.f, q0 = 0.f, q1 = 0.f, q2 = 0.f, q3 = 0.f;
#pragma unroll
        for (int i = 0; i < 56; i += 4) {
          a0[i] = gelu_f(a0[i]); a0[i + 1] = gelu_f(a0[i + 1]); a0[i + 2] = gelu_f(a0[i + 2]); a0[i + 3] = gelu_f(a0[i + 3]);
          a1[i] = gelu_f(a1[i]); a1[i + 1] = gelu_f(a1[i + 1]); a1[i + 2] = gelu_f(a1[i + 2]); a1[i + 3] = gelu_f(a1[i + 3]);
          s0 += a0[i] + a0[i + 1]; s1 += a0[i + 2] + a0[i + 3]; s2 += a1[i] + a1[i + 1]; s3 += a1[i + 2] + a1[i + 3];
          q0 = fmaf(a0[i], a0[i], q0); q0 = fmaf(a0[i + 1], a0[i + 1], q0); q1 = fmaf(a0[i + 2], a0[i + 2], q1); q1 = fmaf(a0[i + 3], a0[i + 3], q1);
          q2 = fmaf(a1[i], a1[i], q2); q2 = fmaf(a1[i + 1], a1[i + 1], q2); q3 = fmaf(a1[i + 2], a1[i + 2], q3); q3 = fmaf(a1[i + 3], a1[i + 3], q3);
        }
        float ms, mq;
        {
          const bool b0 = cq & 1, b1 = cq & 2;
          float t0 = b0 ? s0 : s1, k0 = b0 ? s1 : s0, t1 = b0 ? s2 : s3, k1 = b0 ? s3 : s2;
          float u0 = b0 ? q0 : q1, l0 = b0 ? q1 : q0, u1 = b0 ? q2 : q3, l1 = b0 ? q3 : q2;
          k0 += __shfl_xor_sync(0xffffffffu, t0, 1); k1 += __shfl_xor_sync(0xffffffffu, t1, 1);
          l0 += __shfl_xor_sync(0xffffffffu, u0, 1); l1 += __shfl_xor_sync(0xffffffffu, u1, 1);
          const float t2 = b1 ? k0 : k1, u2 = b1 ? l0 : l1;
          ms = (b1 ? k1 : k0) + __shfl_xor_sync(0xffffffffu, t2, 2);
          mq = (b1 ? l1 : l0) + __shfl_xor_sync(0xffffffffu, u2, 2);
        }
        const int myrow = (cq >> 1) * 64 + w4 * 16 + (cq & 1) * 8 + g;
        const uint32_t tag = (epoch + 1) & 1;
        if (leader) TR(2);
        {
          const unsigned long long v = (unsigned long long)__float_as_uint(ms) | ((unsigned long long)((__float_as_uint(mq) & ~1u) | tag) << 32);
          asm volatile("st.relaxed.gpu.global.u64 [%0], %1;" :: "l"(&g_stats[rb][sl][myrow]), "l"(v) : "memory");
        }
        const uint32_t t0 = clock32();
        uint32_t y0[28], y1[28];
#pragma unroll
        for (int i = 0; i < 28; i++) { y0[i] = pack2(a0[2 * i], a0[2 * i + 1]); y1[i] = pack2(a1[2 * i], a1[2 * i + 1]); asm volatile("" : "+r"(y0[i]), "+r"(y1[i])); }
        while (clock32() - t0 < STATS_DELAY) { }
        if (leader) TR(12);
        float pm[8], pq[8];
        {
          uint32_t it = 0, missing = 0xffu;
          do {
#pragma unroll
            for (int j = 0; j < 8; j++) {
              if (missing & (1u << j)) {
                unsigned long long v;
                asm volatile("ld.relaxed.gpu.global.u64 %0, [%1];" : "=l"(v) : "l"(&g_stats[rb][j][myrow]) : "memory");
                pm[j] = __uint_as_float((uint32_t)v); pq[j] = __uint_as_float((uint32_t)(v >> 32));
              }
            }
#pragma unroll
            for (int j = 0; j < 8; j++) if (__all_sync(0xffffffffu, (__float_as_uint(pq[j]) & 1u) == tag)) missing &= ~(1u << j);
            if (++it > SPIN_LIMIT) TIMEOUT(3002)
          } while (missing);
        }
        __syncwarp();
        if (leader) TR(3);
        const float mean = (((pm[0] + pm[1]) + (pm[2] + pm[3])) + ((pm[4] + pm[5]) + (pm[6] + pm[7]))) * (1.f / 896.f);
        const float ex2 = (((pq[0] + pq[1]) + (pq[2] + pq[3])) + ((pq[4] + pq[5]) + (pq[6] + pq[7]))) * (1.f / 896.f);
        const float rstd = rsqrtf(fmaxf(fmaf(-mean, mean, ex2), 0.f) + 4e-5f);
        const uint32_t rr = pack2(rstd, rstd), cc = pack2(-mean * rstd, -mean * rstd);
        const int qb = lane & ~3;
        const uint32_t r0 = __shfl_sync(0xffffffffu, rr, qb), r1 = __shfl_sync(0xffffffffu, rr, qb + 1), r2 = __shfl_sync(0xffffffffu, rr, qb + 2), r3 = __shfl_sync(0xffffffffu, rr, qb + 3);
        const uint32_t c0 = __shfl_sync(0xffffffffu, cc, qb), c1 = __shfl_sync(0xffffffffu, cc, qb + 1), c2 = __shfl_sync(0xffffffffu, cc, qb + 2), c3 = __shfl_sync(0xffffffffu, cc, qb + 3);
        mbar_wait(bar + 8 * (B_W1EMPTY + 4), 1); mbar_wait(bar + 8 * (B_W1EMPTY + 5), 1);
        const uint32_t sch = 2 * w4 + (mi & 1);
        const uint32_t zb = sb + SM_R + (mcol * 8 + ri) * 128 + ((sch ^ ri) << 4);
#pragma unroll
        for (int nb = 0; nb < 14; nb += 2) {
          const int i = nb * 2;
          stsm4t(zb + nb * 1024, fma_bf2(y0[i], r0, c0), fma_bf2(y0[i + 1], r1, c1), fma_bf2(y0[i + 2], r0, c0), fma_bf2(y0[i + 3], r1, c1));
          if (nb < SPLIT) stsm4t(zb + 14336 + nb * 1024, fma_bf2(y1[i], r2, c2), fma_bf2(y1[i + 1], r3, c3), fma_bf2(y1[i + 2], r2, c2), fma_bf2(y1[i + 3], r3, c3));
        }
        if (leader) TR(4);
        float b0[56], b1[56];
        p1_step<112, true>(b0, b1, sb, 0, 16, false, leader);
#pragma unroll
        for (int nb = SPLIT; nb < 14; nb += 2) {
          const int i = nb * 2;
          stsm4t(zb + 14336 + nb * 1024, fma_bf2(y1[i], r2, c2), fma_bf2(y1[i + 1], r3, c3), fma_bf2(y1[i + 2], r2, c2), fma_bf2(y1[i + 3], r3, c3));
        }
        fence_async_smem();
        __syncwarp();
        if (lane == 0) mbar_arrive(bar + 8 * B_Z2);
        p1_rest<112>(b0, b1, sb, 16, false, leader);
        if (leader) { TR(5); for (int i = 0; i < NSLOT2; i++) mbar_arrive(bar + 8 * (B_P2EMPTY + i)); }
#pragma unroll
          for (int i = 0; i < 28; i++) zf[i] = pack2(gelu_f(b1[2 * i]), gelu_f(b1[2 * i + 1]));
          mbar_wait(bar + 8 * B_RFREE1, 0);
          mbar_wait(bar + 8 * B_KVFREE, 0);
#pragma unroll
          for (int i = 0; i < 7; i++)
            asm volatile("st.shared.v4.u32 [%0], {%1, %2, %3, %4};" :: "r"(sb + SM_Z1X + w4 * 3584 + i * 512 + lane * 16), "r"(zf[4 * i]), "r"(zf[4 * i + 1]), "r"(zf[4 * i + 2]), "r"(zf[4 * i + 3]) : "memory");
#pragma unroll
          for (int i = 0; i < 28; i++) zf[i] = pack2(gelu_f(b0[2 * i]), gelu_f(b0[2 * i + 1]));
          __syncwarp();
          if (lane == 0) mbar_arrive(bar + 8 * B_Z1);
          if (leader) TR(6);
      }
      P2_INIT()
      P2_ISSUE(0)
      P2_RETIRE(0)
      P2_ISSUE(1)
      P2_RETIRE(1)
      P2_ISSUE(2)
      P2_RETIRE(2)
    } else {
      {
        float a0[64], a1[64];
        const uint64_t dX = make_desc(sb + SM_X, 16, 1024, 1);
        const uint64_t dW = make_desc(sb + SM_W, 8192, 1024, 1);
        mbar_wait(bar + 8 * B_ORDER, 0);
#pragma unroll 1
        for (int c = 0; c < 8; c++) {
          const int slot = w_slot(8 + c);
          mbar_wait(bar + 8 * (B_XFULL + c), 0);
          mbar_wait(bar + 8 * (B_W1FULLB + slot), w_full_parity(8 + c));
          if (TRACE2 && leader) TR2(40 + c);
          const uint64_t dx = dX + c * 1024, dw = dW + slot * 1024;
          wgmma_fence();
#pragma unroll
          for (int k = 0; k < 4; k++) {
            wgmma_ss<128, 1, 0>(a0, dw + 128 * k, dx + 2 * k, (c | k) != 0);
            wgmma_ss<128, 1, 0>(a1, dw + 512 + 128 * k, dx + 2 * k, (c | k) != 0);
          }
          wgmma_commit();
          wgmma_wait<1>();
          if (c > 0 && leader) mbar_arrive(bar + 8 * (B_W1EMPTY + w_slot(7 + c)));
        }
        wgmma_wait<0>();
        if (leader) { mbar_arrive(bar + 8 * (B_W1EMPTY + 3)); TR(11); }
        uint32_t fa[32], fb[32];
#pragma unroll
        for (int i = 0; i < 32; i++) { fa[i] = pack2(phi_f(a0[2 * i]), phi_f(a0[2 * i + 1])); fb[i] = pack2(a1[2 * i], a1[2 * i + 1]); }
        float c[KV_CHAINS][12];
#pragma unroll
        for (int j = 0; j < 8; j++) {
          float (&c0)[4] = *reinterpret_cast<float (*)[4]>(&c[j % KV_CHAINS][0]);
          float (&c1)[4] = *reinterpret_cast<float (*)[4]>(&c[j % KV_CHAINS][4]);
          float (&cz)[4] = *reinterpret_cast<float (*)[4]>(&c[j % KV_CHAINS][8]);
          if (j < KV_CHAINS) {
#pragma unroll
            for (int e = 0; e < 12; e++) c[j][e] = 0.f;
          }
          mma16816_acc(c0, fa[4 * j], fa[4 * j + 1], fa[4 * j + 2], fa[4 * j + 3], fb[4 * j], fb[4 * j + 2]);
          mma16816_acc(c1, fa[4 * j], fa[4 * j + 1], fa[4 * j + 2], fa[4 * j + 3], fb[4 * j + 1], fb[4 * j + 3]);
          mma16816_acc(cz, fa[4 * j], fa[4 * j + 1], fa[4 * j + 2], fa[4 * j + 3], 0x3f803f80u, 0x3f803f80u);
        }
#pragma unroll
        for (int j = 1; j < KV_CHAINS; j++)
#pragma unroll
          for (int e = 0; e < 12; e++) c[0][e] += c[j][e];
        if (leader) TR(18);
        {
          const uint32_t d = sb + SM_KVSUM + w4 * 1024 + g * 64 + cq * 8;
          asm volatile("st.shared.v2.f32 [%0], {%1, %2};" :: "r"(d), "f"(c[0][0]), "f"(c[0][1]) : "memory");
          asm volatile("st.shared.v2.f32 [%0], {%1, %2};" :: "r"(d + 512), "f"(c[0][2]), "f"(c[0][3]) : "memory");
          asm volatile("st.shared.v2.f32 [%0], {%1, %2};" :: "r"(d + 32), "f"(c[0][4]), "f"(c[0][5]) : "memory");
          asm volatile("st.shared.v2.f32 [%0], {%1, %2};" :: "r"(d + 544), "f"(c[0][6]), "f"(c[0][7]) : "memory");
          if (cq < 2) asm volatile("st.shared.f32 [%0], %1;" :: "r"(sb + SM_KVS + 1024 + (w4 * 16 + g + cq * 8) * 4), "f"(cq ? c[0][10] : c[0][8]) : "memory");
        }
      }
      {
        float qt[64];
        const uint64_t dX = make_desc(sb + SM_X, 16, 1024, 1);
        const uint64_t dW = make_desc(sb + SM_W, 8192, 1024, 1);
#pragma unroll 1
        for (int i = 0; i < 4; i++) {
          mbar_wait(bar + 8 * (B_W1FULLB + i), w_full_parity(24 + i));
          const uint64_t dx = dX + i * 2048, dw = dW + i * 1024;
          wgmma_fence();
#pragma unroll
          for (int k = 0; k < 8; k++) wgmma_ss<128, 1, 0>(qt, dw + 128 * k, dx + (k >> 2) * 1024 + 2 * (k & 3), (i | k) != 0);
          wgmma_commit();
          if (i == 0) { fence_async_smem(); __syncwarp(); if (lane == 0) mbar_arrive(bar + 8 * B_KVRED); if (leader) TR(17); }
          wgmma_wait<1>();
          if (i > 0 && leader) mbar_arrive(bar + 8 * (B_P2EMPTY + i - 1));
        }
        P2_INIT()
        wgmma_wait<0>();
        if (leader) { mbar_arrive(bar + 8 * (B_P2EMPTY + 3)); mbar_arrive(bar + 8 * (B_P2EMPTY + 4)); TR(14); }
        P2_ISSUE(0)
        mbar_wait(bar + 8 * B_RFREE1, 0);
        const uint32_t ob = sb + SM_OST + (mcol * 8 + ri) * 128 + (((2 * w4 + (mi & 1)) ^ ri) << 4);
#pragma unroll
        for (int nb = 0; nb < 16; nb += 2) {
          const int i = nb * 4;
          stsm4t(ob + nb * 1024, pack2(qt[i], qt[i + 1]), pack2(qt[i + 2], qt[i + 3]), pack2(qt[i + 4], qt[i + 5]), pack2(qt[i + 6], qt[i + 7]));
        }
        __syncwarp();
        if (lane == 0) mbar_arrive(bar + 8 * B_O);
        if (leader) TR(16);
        P2_RETIRE(0)
        P2_ISSUE(1)
        P2_RETIRE(1)
        P2_ISSUE(2)
        mbar_wait(bar + 8 * B_Z1, 0);
#pragma unroll
        for (int i = 0; i < 7; i++)
          asm volatile("ld.shared.v4.u32 {%0, %1, %2, %3}, [%4];" : "=r"(zf[4 * i]), "=r"(zf[4 * i + 1]), "=r"(zf[4 * i + 2]), "=r"(zf[4 * i + 3]) : "r"(sb + SM_Z1X + w4 * 3584 + i * 512 + lane * 16) : "memory");
        __syncwarp();
        if (lane == 0) mbar_arrive(bar + 8 * B_Z1F);
        P2_RETIRE(2)
      }
    }

    {
      const int ostep = O_STEP + 4 * wg;
#pragma unroll 1
      for (int n = 3; n < ostep; n++) { P2_ISSUE(n) P2_RETIRE(n) }
      {
        float on[4][12];
        mbar_wait(bar + 8 * B_KV, 0);
        P2_ISSUE(ostep)
        const uint64_t dq = make_desc(sb + SM_OST + wg * 8192, 16, 1024, 1), dk = make_desc(sb + SM_KVB, 128, 256, 0);
        wgmma_fence();
#pragma unroll
        for (int h = 0; h < 4; h++) wgmma_ss0<24, 0, 1>(on[h], dq + 2 * h, dk + 48 * h);
        wgmma_commit();
        wgmma_wait<2>();
        if (leader) mbar_arrive(bar + 8 * (B_P2EMPTY + sp));
        sp = s;
        if (++s == NSLOT2) { s = 0; ph ^= 1; }
        P2_ISSUE(ostep + 1)
        P2_RETIRE(ostep + 1)
        P2_ISSUE(ostep + 2)
        const uint32_t ob = sb + SM_OST + (wg * 64 + mrow) * 128;
#pragma unroll
        for (int h = 0; h < 4; h++) {
          const float i0 = __fdividef(1.f, on[h][8] + 1e-6f), i1 = __fdividef(1.f, on[h][10] + 1e-6f);
          stsm4(ob + (((2 * h + mcol) ^ ri) << 4), pack2(on[h][0] * i0, on[h][1] * i0), pack2(on[h][2] * i1, on[h][3] * i1), pack2(on[h][4] * i0, on[h][5] * i0), pack2(on[h][6] * i1, on[h][7] * i1));
        }
        P2_RETIRE(ostep + 2)
        P2_ISSUE(ostep + 3)
        fence_async_smem();
        __syncwarp();
        if (lane == 0) mbar_arrive(bar + 8 * B_O2);
        if (leader) TR(34 + wg);
        P2_RETIRE(ostep + 3)
      }
#pragma unroll 1
      for (int n = ostep + 4; n < 31; n++) { P2_ISSUE(n) P2_RETIRE(n) }
      P2_ISSUE(31)
      mbar_wait(bar + 8 * B_OOK, 0);
      P2_RETIRE(31)
      wgmma_wait<0>();
      if (leader) { mbar_arrive(bar + 8 * (B_P2EMPTY + sp)); TR(22 + wg); }
#define H_STAGE(nb) stsm4((nb) < 8 ? sb + SM_R + (wg * 64 + mrow) * 128 + ((((nb) + mcol) ^ ri) << 4) : sb + SM_R + 16384 + (wg * 64 + mrow) * 112 + ((nb) - 8 + mcol) * 16, \
              mul_bf2(zf[2 * (nb)], pack2(acc[4 * (nb)], acc[4 * (nb) + 1])), mul_bf2(zf[2 * (nb) + 1], pack2(acc[4 * (nb) + 2], acc[4 * (nb) + 3])), \
              mul_bf2(zf[2 * (nb) + 2], pack2(acc[4 * (nb) + 4], acc[4 * (nb) + 5])), mul_bf2(zf[2 * (nb) + 3], pack2(acc[4 * (nb) + 6], acc[4 * (nb) + 7])));
#pragma unroll
      for (int nb = 0; nb < 8; nb += 2) H_STAGE(nb)
      if (leader) TR(36 + wg);
      fence_async_smem();
      if (leader) TR(38 + wg);
      __syncwarp();
      if (lane == 0) mbar_arrive(bar + 8 * B_H0);
#pragma unroll
      for (int nb = 8; nb < 14; nb += 2) H_STAGE(nb)
      fence_async_smem();
      __syncwarp();
      if (lane == 0) mbar_arrive(bar + 8 * B_H1);
      if (leader) TR(24 + wg);
    }
    {
      float accA[32], accB[32];
      const uint64_t dB3 = make_desc(sb + 16384, 8192, 1024, 1);
#pragma unroll
      for (int m = 0; m < 8; m++) {
        mbar_wait(bar + 8 * (B_P3FULL + m), 0);
        const uint64_t da = dA2 + slot3(m) * (SLOT3 >> 4), db = dB3 + slot3(m) * (SLOT3 >> 4);
        wgmma_fence();
#pragma unroll
        for (int k = 0; k < 4; k++) { if ((m | k) == 0) wgmma_ss0<64, 0, 1>(accA, da, db); else wgmma_ss<64, 0, 1>(accA, da + 2 * k, db + 128 * k, 1); }
        wgmma_commit();
        wgmma_wait<1>();
        if (m > 0 && leader) mbar_arrive(bar + 8 * (B_P3EMPTY + m - 1));
      }
      if (leader) TR(26 + wg);
      wgmma_wait<0>();
      if (leader) mbar_arrive(bar + 8 * (B_P3EMPTY + 7));
      mbar_wait(bar + 8 * B_GATE, 0);
      const float g0 = reinterpret_cast<const float*>(smem + SM_G)[row0], g1 = reinterpret_cast<const float*>(smem + SM_G)[row0 + 8];
      const float h0 = 0.5f * (1.f - g0), h1 = 0.5f * (1.f - g1);
#pragma unroll
      for (int i = 0; i < 32; i++) { accA[i] *= (i & 2) ? g1 : g0; asm volatile("" : "+f"(accA[i])); }
      const uint64_t dW3 = make_desc(sb, 8192, 1024, 1);
      {
        mbar_wait(bar + 8 * B_WB2, 0);
        const uint64_t da = dA2 + (SM_R >> 4), db = dW3 + (wout_off(0) >> 4);
        wgmma_fence();
#pragma unroll
        for (int k = 0; k < 4; k++) { if (k == 0) wgmma_ss0<64, 0, 1>(accB, da, db); else wgmma_ss<64, 0, 1>(accB, da + 2 * k, db + 128 * k, 1); }
        wgmma_commit();
        mbar_wait(bar + 8 * B_WB0, 0);
      }
#pragma unroll
      for (int n = 0; n < 13; n++) {
        if (n == 8) mbar_wait(bar + 8 * B_WB1, 0);
        mbar_wait(bar + 8 * (B_HFULL + n % 5), (n / 5) & 1);
        if (n == 0 && leader) TR(28 + wg);
        if (TRACE2 && leader) TR2(176 + 16 * wg + n);
        const uint64_t da = dA2 + (hslot_off(n % 5) >> 4), db = dW3 + (wout_off(n + 1) >> 4);
        wgmma_fence();
#pragma unroll
        for (int k = 0; k < 4; k++) wgmma_ss<64, 0, 1>(accB, da + 2 * k, db + 128 * k, 1);
        wgmma_commit();
        if (n < 9) wgmma_wait<1>();
        if (n > 0 && n < 9 && leader) mbar_arrive(bar + 8 * (B_HEMPTY + (n - 1) % 5));
      }
      wgmma_wait<0>();
      if (leader) TR(30 + wg);
      const bool odd = cq & 1;
      __nv_bfloat16* orow = P.p_out + (size_t)(rb * 128 + row0) * DM + sl * 64 + (odd ? 8 : 0) + (cq >> 1) * 4;
#pragma unroll
      for (int nb = 0; nb < 8; nb += 2) {
        const int i = nb * 4;
        const uint32_t p0 = pack2(fmaf(h0, accB[i], accA[i]), fmaf(h0, accB[i + 1], accA[i + 1])), p1 = pack2(fmaf(h1, accB[i + 2], accA[i + 2]), fmaf(h1, accB[i + 3], accA[i + 3]));
        const uint32_t p2 = pack2(fmaf(h0, accB[i + 4], accA[i + 4]), fmaf(h0, accB[i + 5], accA[i + 5])), p3 = pack2(fmaf(h1, accB[i + 6], accA[i + 6]), fmaf(h1, accB[i + 7], accA[i + 7]));
        const uint32_t x0 = __shfl_xor_sync(0xffffffffu, odd ? p0 : p2, 1), x1 = __shfl_xor_sync(0xffffffffu, odd ? p1 : p3, 1);
        *reinterpret_cast<uint2*>(orow + nb * 8) = odd ? make_uint2(x0, p2) : make_uint2(p0, x0);
        *reinterpret_cast<uint2*>(orow + 8 * DM + nb * 8) = odd ? make_uint2(x1, p3) : make_uint2(p1, x1);
      }
      if (leader) {
        if (wg == 0) { g_rb[rb][sl] = epoch + 1; g_sl[sl][rb] = epoch + 1; }
        TR(32 + wg);
      }
    }
  }
}

typedef CUresult (*EncodeFn)(CUtensorMap*, CUtensorMapDataType, cuuint32_t, void*, const cuuint64_t*, const cuuint64_t*, const cuuint32_t*, const cuuint32_t*,
                             CUtensorMapInterleave, CUtensorMapSwizzle, CUtensorMapL2promotion, CUtensorMapFloatOOBfill);

void make2d(EncodeFn enc, CUtensorMap* m, const void* base, uint64_t d0, uint64_t d1, uint32_t b0, uint32_t b1, CUtensorMapSwizzle swz,
            CUtensorMapL2promotion promo = CU_TENSOR_MAP_L2_PROMOTION_L2_128B) {
  cuuint64_t dims[2] = {d0, d1}; cuuint64_t strides[1] = {d0 * 2}; cuuint32_t box[2] = {b0, b1}; cuuint32_t es[2] = {1, 1};
  CUresult r = enc(m, CU_TENSOR_MAP_DATA_TYPE_BFLOAT16, 2, const_cast<void*>(base), dims, strides, box, es, CU_TENSOR_MAP_INTERLEAVE_NONE, swz,
      promo, CU_TENSOR_MAP_FLOAT_OOB_FILL_NONE);
  (void)r;
}

}

extern "C" void kernel_launch(void* const* d_in, const int* in_sizes, int n_in, void* d_out, int out_size) {
  static EncodeFn enc = nullptr;
  static int num_sms = 0;
  static void *z2p = nullptr, *op = nullptr, *hp = nullptr;
  if (!enc) {
    void* fn = nullptr; cudaDriverEntryPointQueryResult st;
    cudaGetDriverEntryPoint("cuTensorMapEncodeTiled", &fn, cudaEnableDefault, &st);
    enc = (EncodeFn)fn;
    int dev = 0; cudaGetDevice(&dev);
    cudaDeviceGetAttribute(&num_sms, cudaDevAttrMultiProcessorCount, dev);
    cudaFuncSetAttribute(fused_kernel<true>, cudaFuncAttributeMaxDynamicSharedMemorySize, SM_TOTAL);
    cudaFuncSetAttribute(fused_kernel<false>, cudaFuncAttributeMaxDynamicSharedMemorySize, SM_TOTAL);
    cudaGetSymbolAddress(&z2p, g_z2T); cudaGetSymbolAddress(&op, g_O); cudaGetSymbolAddress(&hp, g_H);
  }
  const __nv_bfloat16* x = (const __nv_bfloat16*)d_in[0];
  const __nv_bfloat16* wqkv = (const __nv_bfloat16*)d_in[1];
  const __nv_bfloat16* wo = (const __nv_bfloat16*)d_in[2];
  const __nv_bfloat16* win = (const __nv_bfloat16*)d_in[4];
  const __nv_bfloat16* wsp = (const __nv_bfloat16*)d_in[5];
  const __nv_bfloat16* bsp = (const __nv_bfloat16*)d_in[6];
  const __nv_bfloat16* wout = (const __nv_bfloat16*)d_in[7];
  const __nv_bfloat16* gw = (const __nv_bfloat16*)d_in[8];
  Params P;
  const CUtensorMapSwizzle S128 = CU_TENSOR_MAP_SWIZZLE_128B;
  make2d(enc, &P.x, x, DM, SEQ, 64, 128, S128);
  make2d(enc, &P.win, win, 2 * FH, 512, 64, 64, S128);
  {
    cuuint64_t dims[4] = {48, 8, 2, 512}; cuuint64_t strides[3] = {96, 1792, 3584}; cuuint32_t box[4] = {64, 1, 1, 64}; cuuint32_t es[4] = {1, 1, 1, 1};
    enc(&P.win2, CU_TENSOR_MAP_DATA_TYPE_BFLOAT16, 4, const_cast<__nv_bfloat16*>(win) + 512, dims, strides, box, es, CU_TENSOR_MAP_INTERLEAVE_NONE, S128,
        CU_TENSOR_MAP_L2_PROMOTION_L2_128B, CU_TENSOR_MAP_FLOAT_OOB_FILL_NONE);
  }
  make2d(enc, &P.wqkv, wqkv, 1536, 512, 64, 64, S128);
  make2d(enc, &P.wsp, wsp, SEQ, SEQ, 64, 128, S128);
  make2d(enc, &P.z2, z2p, SEQ, FH, 64, 112, S128);
  make2d(enc, &P.z2s, z2p, SEQ, FH, 64, Z2_ROWS, S128);
  make2d(enc, &P.o, op, DM, SEQ, 64, 128, S128);
  make2d(enc, &P.os, op, DM, SEQ, 64, 32, S128);
  make2d(enc, &P.hst, hp, FH, SEQ, 64, 128, S128);
  {
    cuuint64_t dims[3] = {48, 8, SEQ}; cuuint64_t strides[2] = {96, 1792}; cuuint32_t box[3] = {56, 1, 128}; cuuint32_t es[3] = {1, 1, 1};
    enc(&P.hst2, CU_TENSOR_MAP_DATA_TYPE_BFLOAT16, 3, (__nv_bfloat16*)hp + 512, dims, strides, box, es, CU_TENSOR_MAP_INTERLEAVE_NONE, CU_TENSOR_MAP_SWIZZLE_NONE,
        CU_TENSOR_MAP_L2_PROMOTION_L2_128B, CU_TENSOR_MAP_FLOAT_OOB_FILL_NONE);
  }
  make2d(enc, &P.hld, hp, FH, SEQ, 64, 128, S128);
  make2d(enc, &P.wo, wo, DM, DM, 64, 64, S128);
  make2d(enc, &P.wout, wout, DM, FH, 64, 64, S128);
  P.p_x = x; P.p_wqkv = wqkv; P.p_win = win; P.p_wsp = wsp; P.p_wo = wo; P.p_wout = wout; P.p_bsp = bsp; P.p_gw = gw; P.p_out = (__nv_bfloat16*)d_out;
  if (num_sms == 132) fused_kernel<true><<<132, NTHREADS, SM_TOTAL>>>(P);
  else fused_kernel<false><<<128, NTHREADS, SM_TOTAL>>>(P);
}
```
